```python
import torch

def _softmax(x, axis=-1):
    return torch.softmax(x, dim=axis)
def _gelu(x):
    return torch.nn.functional.gelu(x, approximate="tanh")
def _silu(x):
    return torch.nn.functional.silu(x)
def _sigmoid(x):
    return torch.sigmoid(x)
def _layernorm(x, axis=-1, eps=1e-5):
    m = x.mean(dim=axis, keepdim=True)
    v = x.var(dim=axis, keepdim=True, unbiased=False)
    return (x - m) / torch.sqrt(v + eps)
def _scatter_add(tgt, idx, src, axis=0):
    return tgt.clone().index_add_(axis, idx, src)
def _segment_sum(src, seg, n):
    out = torch.zeros((n,) + src.shape[1:], dtype=src.dtype)
    return out.index_add_(0, seg, src)
def _pad(x, pw):
    flat = tuple(v for pair in reversed(pw) for v in pair)
    return torch.nn.functional.pad(x, flat)

kernel_name = 'concat_heads__mha_block__softmax_full_mha__prompt'

def setup_inputs():

    _w = (lambda a: (lambda t: t.to(torch.bfloat16) if t.is_floating_point() else t)(torch.as_tensor(a)))
    def _A_setup():
        B, S, D, H = 1, 2048, 1024, 32
        return {
            "x": _w((lambda *s: torch.randn(*s, dtype=torch.bfloat16) * 0.2)(B, S, D)),
            "wqkv": _w((lambda *s: torch.randn(*s, dtype=torch.bfloat16) * 0.2)(D, 3 * D)),
            "wo": _w((lambda *s: torch.randn(*s, dtype=torch.bfloat16) * 0.05)(D, D)),
        }
    _A_in = _A_setup()

    def _B_setup():
        B, S, D = 1, 2048, 1024
        return {
            "x": _w((lambda *s: torch.randn(*s, dtype=torch.bfloat16) * 0.2)(B, S, D)),
            "wqkv": _w((lambda *s: torch.randn(*s, dtype=torch.bfloat16) * 0.2)(D, 3 * D)),
            "wo": _w((lambda *s: torch.randn(*s, dtype=torch.bfloat16) * 0.05)(D, D)),
        }
    _B_in = _B_setup()

    return {
        "A_x": _A_in["x"],
        "A_wqkv": _A_in["wqkv"],
        "A_wo": _A_in["wo"],
        "B_x": _B_in["x"],
        "B_wqkv": _B_in["wqkv"],
        "B_wo": _B_in["wo"],
    }

def reference(A_x, A_wqkv, A_wo, B_x, B_wqkv, B_wo):
    def _A_ref(x, wqkv, wo):
        B, S, D = x.shape
        H = 32
        Dh = D // H
        qkv = (lambda x, *d: x.permute(*d))((x @ wqkv).reshape(B, S, 3, H, Dh), 2, 0, 3, 1, 4)
        q, k, v = qkv[0], qkv[1], qkv[2]
        scores = torch.einsum("bhqd,bhkd->bhqk", q, k) * (Dh ** -0.5)
        p = _softmax(scores, axis=-1)
        o = torch.einsum("bhqk,bhkd->bhqd", p, v)
        return (lambda x, *d: x.permute(*d))(o, 0, 2, 1, 3).reshape(B, S, D) @ wo

    def _B_ref(x, wqkv, wo):
        B, S, D = x.shape
        H = 32; Dh = D // H
        qkv = (lambda x, *d: x.permute(*d))((x @ wqkv).reshape(B, S, 3, H, Dh), 2, 0, 3, 1, 4)
        q, k, v = qkv[0], qkv[1], qkv[2]
        scale = Dh ** -0.5
        scores = torch.einsum("bhqd,bhkd->bhqk", q, k) * scale
        p = _softmax(scores, axis=-1)
        o = torch.einsum("bhqk,bhkd->bhqd", p, v)
        return (lambda x, *d: x.permute(*d))(o, 0, 2, 1, 3).reshape(B, S, D) @ wo

    a = _A_ref(A_x, A_wqkv, A_wo)
    b = _B_ref(B_x, B_wqkv, B_wo)
    return torch.concatenate([a, b], axis=-1)
```

```cpp
#include <cuda_runtime.h>
#include <cuda_bf16.h>
#include <cuda.h>
#include <stdint.h>

namespace {

constexpr int SEQ = 2048, DM = 1024, NH = 32, DH = 32, NQKV = 3 * DM;

__device__ __align__(1024) __nv_bfloat16 g_qk[2 * SEQ * 2 * DM];
__device__ __align__(1024) __nv_bfloat16 g_vt[2 * DM * SEQ];
__device__ __align__(1024) __nv_bfloat16 g_o[2 * SEQ * DM];
__device__ __align__(16) uint32_t g_nrm[2 * 3 * NH * (SEQ / 16)];

struct Sync { int exits, qkv_done[8], o_done[64]; };
__device__ Sync g_sync;

__device__ __forceinline__ uint32_t smem_u32(const void* p) { return (uint32_t)__cvta_generic_to_shared(p); }

__device__ __forceinline__ void mbar_init(uint32_t bar, uint32_t count) {
  asm volatile("mbarrier.init.shared::cta.b64 [%0], %1;" ::"r"(bar), "r"(count) : "memory");
}
__device__ __forceinline__ void mbar_expect_tx(uint32_t bar, uint32_t bytes) {
  asm volatile("mbarrier.arrive.expect_tx.shared::cta.b64 _, [%0], %1;" ::"r"(bar), "r"(bytes) : "memory");
}
__device__ __forceinline__ void mbar_arrive(uint32_t bar) {
  asm volatile("mbarrier.arrive.shared::cta.b64 _, [%0];" ::"r"(bar) : "memory");
}
__device__ __forceinline__ bool mbar_try(uint32_t bar, uint32_t parity) {
  uint32_t ok;
  asm volatile("{\n.reg .pred p;\nmbarrier.try_wait.parity.shared::cta.b64 p, [%1], %2;\nselp.u32 %0, 1, 0, p;\n}\n"
               : "=r"(ok) : "r"(bar), "r"(parity) : "memory");
  return ok;
}
__device__ __forceinline__ bool mbar_test(uint32_t bar, uint32_t parity) {
  uint32_t ok;
  asm volatile("{\n.reg .pred p;\nmbarrier.test_wait.parity.shared::cta.b64 p, [%1], %2;\nselp.u32 %0, 1, 0, p;\n}\n"
               : "=r"(ok) : "r"(bar), "r"(parity) : "memory");
  return ok;
}
__device__ __forceinline__ void give_up() { asm volatile("exit;"); }
__device__ __forceinline__ void mbar_wait(uint32_t bar, uint32_t parity) {
  for (uint32_t i = 0; i < (1u << 18); i++)
    if (mbar_try(bar, parity)) break;
}
template <int NS = 128>
__device__ __forceinline__ void mbar_wait_sleep(uint32_t bar, uint32_t parity) {
  for (uint32_t i = 0; !mbar_try(bar, parity); i++) {
    __nanosleep(NS);
    if (i > (1u << 18)) give_up();
  }
}
__device__ __forceinline__ void tma_load_2d(uint32_t dst, const CUtensorMap* map, int c0, int c1, uint32_t bar) {
  asm volatile("cp.async.bulk.tensor.2d.shared::cluster.global.mbarrier::complete_tx::bytes [%0], [%1, {%3, %4}], [%2];"
               ::"r"(dst), "l"(map), "r"(bar), "r"(c0), "r"(c1) : "memory");
}
__device__ __forceinline__ void tma_store_2d(const CUtensorMap* map, uint32_t src, int c0, int c1) {
  asm volatile("cp.async.bulk.tensor.2d.global.shared::cta.bulk_group [%0, {%2, %3}], [%1];"
               ::"l"(map), "r"(src), "r"(c0), "r"(c1) : "memory");
}
__device__ __forceinline__ void bulk_commit() { asm volatile("cp.async.bulk.commit_group;" ::: "memory"); }
template <int N> __device__ __forceinline__ void bulk_wait_read() { asm volatile("cp.async.bulk.wait_group.read %0;" ::"n"(N) : "memory"); }
template <int N> __device__ __forceinline__ void bulk_wait() { asm volatile("cp.async.bulk.wait_group %0;" ::"n"(N) : "memory"); }
__device__ __forceinline__ void fence_async_smem() { asm volatile("fence.proxy.async.shared::cta;" ::: "memory"); }
__device__ __forceinline__ void fence_async_global() { asm volatile("fence.proxy.async.global;" ::: "memory"); }
__device__ __forceinline__ void signal_add(int* p) { asm volatile("red.release.gpu.global.add.s32 [%0], 1;" ::"l"(p) : "memory"); }
__device__ __forceinline__ void wait_count(const int* p, int target) {
  for (uint32_t i = 0;; i++) {
    int v;
    asm volatile("ld.acquire.gpu.global.s32 %0, [%1];" : "=r"(v) : "l"(p) : "memory");
    if (v >= target) return;
    __nanosleep(200);
    if (i > (1u << 16)) give_up();
  }
}
__device__ __forceinline__ uint32_t lds(uint32_t a) { uint32_t v; asm volatile("ld.shared.u32 %0, [%1];" : "=r"(v) : "r"(a) : "memory"); return v; }
__device__ __forceinline__ uint32_t lds_if(bool ok, uint32_t a) {
  uint32_t v;
  asm volatile("{\n.reg .pred p;\nsetp.ne.u32 p, %2, 0;\nmov.u32 %0, 0;\n@p ld.shared.u32 %0, [%1];\n}\n"
               : "=r"(v) : "r"(a), "r"((uint32_t)ok) : "memory");
  return v;
}
__device__ __forceinline__ void sts(uint32_t a, uint32_t v) { asm volatile("st.shared.u32 [%0], %1;" ::"r"(a), "r"(v) : "memory"); }
__device__ __forceinline__ void fence_mbar_init() { asm volatile("fence.mbarrier_init.release.cluster;" ::: "memory"); }
template <int N> __device__ __forceinline__ void reg_dec() { asm volatile("setmaxnreg.dec.sync.aligned.u32 %0;" ::"n"(N)); }
template <int N> __device__ __forceinline__ void reg_inc() { asm volatile("setmaxnreg.inc.sync.aligned.u32 %0;" ::"n"(N)); }

__device__ __forceinline__ bool elect_one() {
  uint32_t ok;
  asm volatile("{\n.reg .pred p;\nelect.sync _|p, 0xffffffff;\nselp.u32 %0, 1, 0, p;\n}\n" : "=r"(ok));
  return ok;
}
__device__ __forceinline__ void wg_fence() { asm volatile("wgmma.fence.sync.aligned;" ::: "memory"); }
__device__ __forceinline__ void wg_commit() { asm volatile("wgmma.commit_group.sync.aligned;" ::: "memory"); }
template <int N> __device__ __forceinline__ void wg_wait() { asm volatile("wgmma.wait_group.sync.aligned %0;" ::"n"(N) : "memory"); }
template <int N> __device__ __forceinline__ void pin(float (&d)[N]) {
#pragma unroll
  for (int i = 0; i < N; i++) asm volatile("" : "+f"(d[i])::"memory");
}
template <int N> __device__ __forceinline__ void pin(uint32_t (&d)[N]) {
#pragma unroll
  for (int i = 0; i < N; i++) asm volatile("" : "+r"(d[i])::"memory");
}
__host__ __device__ __forceinline__ uint64_t make_desc(uint32_t addr, uint32_t lbo, uint32_t sbo, uint32_t sw) {
  return (uint64_t)((addr & 0x3FFFF) >> 4) | ((uint64_t)(lbo >> 4) << 16) | ((uint64_t)(sbo >> 4) << 32) | ((uint64_t)sw << 62);
}
__device__ __forceinline__ void stsm_x4_t(uint32_t addr, uint32_t r0, uint32_t r1, uint32_t r2, uint32_t r3) {
  asm volatile("stmatrix.sync.aligned.m8n8.x4.trans.shared.b16 [%0], {%1, %2, %3, %4};"
               ::"r"(addr), "r"(r0), "r"(r1), "r"(r2), "r"(r3) : "memory");
}
__device__ __forceinline__ void stsm_x4(uint32_t addr, uint32_t r0, uint32_t r1, uint32_t r2, uint32_t r3) {
  asm volatile("stmatrix.sync.aligned.m8n8.x4.shared.b16 [%0], {%1, %2, %3, %4};"
               ::"r"(addr), "r"(r0), "r"(r1), "r"(r2), "r"(r3) : "memory");
}
__device__ __forceinline__ float ex2(float x) { float y; asm("ex2.approx.ftz.f32 %0, %1;" : "=f"(y) : "f"(x)); return y; }
__device__ __forceinline__ uint32_t pack_bf16(float lo, float hi) {
  uint32_t r; asm("cvt.rn.bf16x2.f32 %0, %1, %2;" : "=r"(r) : "f"(hi), "f"(lo)); return r;
}
__device__ __forceinline__ uint32_t hfma2_bf16(uint32_t a, uint32_t b, uint32_t c) {
  uint32_t r; asm("fma.rn.bf16x2 %0, %1, %2, %3;" : "=r"(r) : "r"(a), "r"(b), "r"(c)); return r;
}

template <int OA, int OB>
__device__ __forceinline__ void wgmma_ss_n256_tb(float (&d)[128], uint64_t da, uint64_t db, int scale_d) {
  asm volatile("{\n.reg .pred p;\n.reg .b64 da, db;\nsetp.ne.b32 p, %130, 0;\nadd.s64 da, %128, %131;\nadd.s64 db, %129, %132;\n"
      "wgmma.mma_async.sync.aligned.m64n256k16.f32.bf16.bf16 {"
      "%0, %1, %2, %3, %4, %5, %6, %7, %8, %9, %10, %11, %12, %13, %14, %15, "
      "%16, %17, %18, %19, %20, %21, %22, %23, %24, %25, %26, %27, %28, %29, %30, %31, "
      "%32, %33, %34, %35, %36, %37, %38, %39, %40, %41, %42, %43, %44, %45, %46, %47, "
      "%48, %49, %50, %51, %52, %53, %54, %55, %56, %57, %58, %59, %60, %61, %62, %63, "
      "%64, %65, %66, %67, %68, %69, %70, %71, %72, %73, %74, %75, %76, %77, %78, %79, "
      "%80, %81, %82, %83, %84, %85, %86, %87, %88, %89, %90, %91, %92, %93, %94, %95, "
      "%96, %97, %98, %99, %100, %101, %102, %103, %104, %105, %106, %107, %108, %109, %110, %111, "
      "%112, %113, %114, %115, %116, %117, %118, %119, %120, %121, %122, %123, %124, %125, %126, %127"
      "}, da, db, p, 1, 1, 0, 1;\n}\n"
      : "+f"(d[0]), "+f"(d[1]), "+f"(d[2]), "+f"(d[3]), "+f"(d[4]), "+f"(d[5]), "+f"(d[6]), "+f"(d[7]),
        "+f"(d[8]), "+f"(d[9]), "+f"(d[10]), "+f"(d[11]), "+f"(d[12]), "+f"(d[13]), "+f"(d[14]), "+f"(d[15]),
        "+f"(d[16]), "+f"(d[17]), "+f"(d[18]), "+f"(d[19]), "+f"(d[20]), "+f"(d[21]), "+f"(d[22]), "+f"(d[23]),
        "+f"(d[24]), "+f"(d[25]), "+f"(d[26]), "+f"(d[27]), "+f"(d[28]), "+f"(d[29]), "+f"(d[30]), "+f"(d[31]),
        "+f"(d[32]), "+f"(d[33]), "+f"(d[34]), "+f"(d[35]), "+f"(d[36]), "+f"(d[37]), "+f"(d[38]), "+f"(d[39]),
        "+f"(d[40]), "+f"(d[41]), "+f"(d[42]), "+f"(d[43]), "+f"(d[44]), "+f"(d[45]), "+f"(d[46]), "+f"(d[47]),
        "+f"(d[48]), "+f"(d[49]), "+f"(d[50]), "+f"(d[51]), "+f"(d[52]), "+f"(d[53]), "+f"(d[54]), "+f"(d[55]),
        "+f"(d[56]), "+f"(d[57]), "+f"(d[58]), "+f"(d[59]), "+f"(d[60]), "+f"(d[61]), "+f"(d[62]), "+f"(d[63]),
        "+f"(d[64]), "+f"(d[65]), "+f"(d[66]), "+f"(d[67]), "+f"(d[68]), "+f"(d[69]), "+f"(d[70]), "+f"(d[71]),
        "+f"(d[72]), "+f"(d[73]), "+f"(d[74]), "+f"(d[75]), "+f"(d[76]), "+f"(d[77]), "+f"(d[78]), "+f"(d[79]),
        "+f"(d[80]), "+f"(d[81]), "+f"(d[82]), "+f"(d[83]), "+f"(d[84]), "+f"(d[85]), "+f"(d[86]), "+f"(d[87]),
        "+f"(d[88]), "+f"(d[89]), "+f"(d[90]), "+f"(d[91]), "+f"(d[92]), "+f"(d[93]), "+f"(d[94]), "+f"(d[95]),
        "+f"(d[96]), "+f"(d[97]), "+f"(d[98]), "+f"(d[99]), "+f"(d[100]), "+f"(d[101]), "+f"(d[102]), "+f"(d[103]),
        "+f"(d[104]), "+f"(d[105]), "+f"(d[106]), "+f"(d[107]), "+f"(d[108]), "+f"(d[109]), "+f"(d[110]), "+f"(d[111]),
        "+f"(d[112]), "+f"(d[113]), "+f"(d[114]), "+f"(d[115]), "+f"(d[116]), "+f"(d[117]), "+f"(d[118]), "+f"(d[119]),
        "+f"(d[120]), "+f"(d[121]), "+f"(d[122]), "+f"(d[123]), "+f"(d[124]), "+f"(d[125]), "+f"(d[126]), "+f"(d[127])
      : "l"(da), "l"(db), "r"(scale_d), "n"(OA), "n"(OB));
}
template <int OA, int OB>
__device__ __forceinline__ void wgmma_ss_n192_tb(float (&d)[96], uint64_t da, uint64_t db, int scale_d) {
  asm volatile("{\n.reg .pred p;\n.reg .b64 da, db;\nsetp.ne.b32 p, %98, 0;\nadd.s64 da, %96, %99;\nadd.s64 db, %97, %100;\n"
      "wgmma.mma_async.sync.aligned.m64n192k16.f32.bf16.bf16 {"
      "%0, %1, %2, %3, %4, %5, %6, %7, %8, %9, %10, %11, %12, %13, %14, %15, "
      "%16, %17, %18, %19, %20, %21, %22, %23, %24, %25, %26, %27, %28, %29, %30, %31, "
      "%32, %33, %34, %35, %36, %37, %38, %39, %40, %41, %42, %43, %44, %45, %46, %47, "
      "%48, %49, %50, %51, %52, %53, %54, %55, %56, %57, %58, %59, %60, %61, %62, %63, "
      "%64, %65, %66, %67, %68, %69, %70, %71, %72, %73, %74, %75, %76, %77, %78, %79, "
      "%80, %81, %82, %83, %84, %85, %86, %87, %88, %89, %90, %91, %92, %93, %94, %95"
      "}, da, db, p, 1, 1, 0, 1;\n}\n"
      : "+f"(d[0]), "+f"(d[1]), "+f"(d[2]), "+f"(d[3]), "+f"(d[4]), "+f"(d[5]), "+f"(d[6]), "+f"(d[7]),
        "+f"(d[8]), "+f"(d[9]), "+f"(d[10]), "+f"(d[11]), "+f"(d[12]), "+f"(d[13]), "+f"(d[14]), "+f"(d[15]),
        "+f"(d[16]), "+f"(d[17]), "+f"(d[18]), "+f"(d[19]), "+f"(d[20]), "+f"(d[21]), "+f"(d[22]), "+f"(d[23]),
        "+f"(d[24]), "+f"(d[25]), "+f"(d[26]), "+f"(d[27]), "+f"(d[28]), "+f"(d[29]), "+f"(d[30]), "+f"(d[31]),
        "+f"(d[32]), "+f"(d[33]), "+f"(d[34]), "+f"(d[35]), "+f"(d[36]), "+f"(d[37]), "+f"(d[38]), "+f"(d[39]),
        "+f"(d[40]), "+f"(d[41]), "+f"(d[42]), "+f"(d[43]), "+f"(d[44]), "+f"(d[45]), "+f"(d[46]), "+f"(d[47]),
        "+f"(d[48]), "+f"(d[49]), "+f"(d[50]), "+f"(d[51]), "+f"(d[52]), "+f"(d[53]), "+f"(d[54]), "+f"(d[55]),
        "+f"(d[56]), "+f"(d[57]), "+f"(d[58]), "+f"(d[59]), "+f"(d[60]), "+f"(d[61]), "+f"(d[62]), "+f"(d[63]),
        "+f"(d[64]), "+f"(d[65]), "+f"(d[66]), "+f"(d[67]), "+f"(d[68]), "+f"(d[69]), "+f"(d[70]), "+f"(d[71]),
        "+f"(d[72]), "+f"(d[73]), "+f"(d[74]), "+f"(d[75]), "+f"(d[76]), "+f"(d[77]), "+f"(d[78]), "+f"(d[79]),
        "+f"(d[80]), "+f"(d[81]), "+f"(d[82]), "+f"(d[83]), "+f"(d[84]), "+f"(d[85]), "+f"(d[86]), "+f"(d[87]),
        "+f"(d[88]), "+f"(d[89]), "+f"(d[90]), "+f"(d[91]), "+f"(d[92]), "+f"(d[93]), "+f"(d[94]), "+f"(d[95])
      : "l"(da), "l"(db), "r"(scale_d), "n"(OA), "n"(OB));
}
template <int OA, int OB>
__device__ __forceinline__ void wgmma_ss_n64(float (&d)[32], uint64_t da, uint64_t db, int scale_d) {
  asm volatile("{\n.reg .pred p;\n.reg .b64 da, db;\nsetp.ne.b32 p, %34, 0;\nadd.s64 da, %32, %35;\nadd.s64 db, %33, %36;\n"
      "wgmma.mma_async.sync.aligned.m64n64k16.f32.bf16.bf16 {"
      "%0, %1, %2, %3, %4, %5, %6, %7, %8, %9, %10, %11, %12, %13, %14, %15, "
      "%16, %17, %18, %19, %20, %21, %22, %23, %24, %25, %26, %27, %28, %29, %30, %31"
      "}, da, db, p, 1, 1, 0, 0;\n}\n"
      : "+f"(d[0]), "+f"(d[1]), "+f"(d[2]), "+f"(d[3]), "+f"(d[4]), "+f"(d[5]), "+f"(d[6]), "+f"(d[7]),
        "+f"(d[8]), "+f"(d[9]), "+f"(d[10]), "+f"(d[11]), "+f"(d[12]), "+f"(d[13]), "+f"(d[14]), "+f"(d[15]),
        "+f"(d[16]), "+f"(d[17]), "+f"(d[18]), "+f"(d[19]), "+f"(d[20]), "+f"(d[21]), "+f"(d[22]), "+f"(d[23]),
        "+f"(d[24]), "+f"(d[25]), "+f"(d[26]), "+f"(d[27]), "+f"(d[28]), "+f"(d[29]), "+f"(d[30]), "+f"(d[31])
      : "l"(da), "l"(db), "r"(scale_d), "n"(OA), "n"(OB));
}
template <int OB>
__device__ __forceinline__ void wgmma_rs_n40(float (&d)[20], uint32_t a0, uint32_t a1, uint32_t a2, uint32_t a3, uint64_t db, int scale_d) {
  asm volatile("{\n.reg .pred p;\n.reg .b64 da, db;\nsetp.ne.b32 p, %25, 0;\nadd.s64 db, %24, %26;\n"
      "wgmma.mma_async.sync.aligned.m64n40k16.f32.bf16.bf16 {"
      "%0, %1, %2, %3, %4, %5, %6, %7, %8, %9, %10, %11, %12, %13, %14, %15, "
      "%16, %17, %18, %19"
      "}, {%20, %21, %22, %23}, db, p, 1, 1, 0;\n}\n"
      : "+f"(d[0]), "+f"(d[1]), "+f"(d[2]), "+f"(d[3]), "+f"(d[4]), "+f"(d[5]), "+f"(d[6]), "+f"(d[7]),
        "+f"(d[8]), "+f"(d[9]), "+f"(d[10]), "+f"(d[11]), "+f"(d[12]), "+f"(d[13]), "+f"(d[14]), "+f"(d[15]),
        "+f"(d[16]), "+f"(d[17]), "+f"(d[18]), "+f"(d[19])
      : "r"(a0), "r"(a1), "r"(a2), "r"(a3), "l"(db), "r"(scale_d), "n"(OB));
}

constexpr uint32_t SB = 1024;
constexpr int NCTA = 128, NHELP = 4;
constexpr int G_BM = 128, G_BN = 256, G_BK = 64, G_STAGES = 4, G_KB = DM / G_BK;
constexpr int G_STAGE_BYTES = (G_BM + G_BN) * G_BK * 2;
constexpr int QKV_NT = NQKV / G_BN, QKV_PER_CTA = 3;
constexpr float Q_SCALE = 0.17677669529663687f * 1.4426950408889634f;
constexpr int A_STAGES = 4, A_KV_BYTES = 18432, A_KV_TX = 16384, A_Q_BYTES = 16384, A_NKB = SEQ / 128, A_PER_CTA = 4;
constexpr uint32_t OFF_STG = SB + G_STAGES * G_STAGE_BYTES, OFF_BAR = OFF_STG + 32768;
constexpr uint32_t OFF_Q0 = SB, OFF_KV = SB + A_Q_BYTES, OFF_Q1 = OFF_STG, OFF_O = OFF_STG + 16384;
static_assert(A_Q_BYTES + A_STAGES * A_KV_BYTES <= 2 * G_STAGE_BYTES, "attention buffers must fit GEMM stages 0 and 1");
constexpr uint32_t B_GFULL = OFF_BAR, B_GEMPTY = B_GFULL + 8 * G_STAGES, B_SFULL = B_GEMPTY + 8 * G_STAGES, B_SEMPTY = B_SFULL + 32;
constexpr uint32_t B_KFULL = B_SEMPTY + 16, B_KEMPTY = B_KFULL + 8 * A_STAGES, B_QFULL = B_KEMPTY + 8 * A_STAGES;
constexpr uint32_t B_QEMPTY = B_QFULL + 16, B_DUMMY = B_QEMPTY + 16, B_ADONE = B_DUMMY + 8;
constexpr uint32_t B_AREADY = B_ADONE + 8, B_STGFREE = B_AREADY + 8;
constexpr uint32_t I_FAST = OFF_BAR + 256, I_CONST = I_FAST + 16;
constexpr uint32_t OFF_DUMP = OFF_BAR + 512;
constexpr int SMEM_BYTES = OFF_DUMP + 512 - SB;

struct Params {
  CUtensorMap x[2], wqkv[2], wo[2], o_ld;
  CUtensorMap qk_st, vt_st, out_st;
  CUtensorMap q_ld, k_ld, vt_ld, o_st;
  uint64_t desc[A_STAGES][16];
  uint64_t dq[4][4];
};

template <bool V> struct BoolC { __device__ constexpr operator bool() const { return V; } };
struct Tile { int br, mt, kind, col0, cstep, nbox; };
__device__ __forceinline__ bool is_helper() { return blockIdx.x >= NCTA; }
__device__ __forceinline__ int phase1_tiles() { return is_helper() ? 8 : QKV_PER_CTA; }
__device__ __forceinline__ Tile phase1_tile(int i) {
  if (is_helper()) {
    const int mt = (blockIdx.x - NCTA) * 4 + (i & 3);
    return i < 4 ? Tile{1, mt, 2, 192, 256, 4} : Tile{0, mt, 3, 192, 256, 4};
  }
  const int t = blockIdx.x + i * NCTA, br = t >= 16 * QKV_NT, r = t - br * 16 * QKV_NT;
  const int nt = (int)((br ? 0xBA9832107654ull : 0xB73A69584210ull) >> (4 * (r >> 4))) & 15;
  return Tile{br, r & 15, nt >> 2, (nt & 3) * G_BN, 64, (br && nt >= 8 && gridDim.x > NCTA) ? 3 : 4};
}
__device__ __forceinline__ Tile out_tile() {
  const int br = blockIdx.x >> 6;
  return Tile{br, ((int)blockIdx.x >> 2) & 15, 3, ((int)blockIdx.x & 3) * G_BN, 64, (!br && gridDim.x > NCTA) ? 3 : 4};
}
__device__ __forceinline__ int qkv_target(int br) { return (br && gridDim.x > NCTA) ? 128 : 96; }
struct Unit { int br, head, qb; };
__device__ __forceinline__ Unit attn_unit(int i) {
  const int u = (blockIdx.x ^ 64) + (i & 1) * NCTA;
  return Unit{i >> 1, u >> 3, u & 7};
}
__device__ __forceinline__ void leave() {
  __threadfence();
  if (atomicAdd(&g_sync.exits, 1) == 4 * (int)gridDim.x - 1) {
    g_sync.exits = 0;
    for (int i = 0; i < 8; i++) g_sync.qkv_done[i] = 0;
    for (int i = 0; i < 64; i++) g_sync.o_done[i] = 0;
  }
}
__device__ __forceinline__ uint32_t hadd2_bf16(uint32_t a, uint32_t b) {
  uint32_t r; asm("add.rn.bf16x2 %0, %1, %2;" : "=r"(r) : "r"(a), "r"(b)); return r;
}

__device__ __forceinline__ uint32_t exp2_pair_alu(float s0, float s1, uint32_t c_sel, uint32_t c_alpha) {
  const float M = 49152.f + 86.f;
  const uint32_t t0 = __float_as_uint(s0 + M), t1 = __float_as_uint(s1 + M);
  uint32_t y, e, q, r;
  asm("prmt.b32 %0, %1, %2, %3;" : "=r"(y) : "r"(t0), "r"(t1), "r"(c_sel));
  asm("prmt.b32 %0, %1, %2, 0x5A1A;" : "=r"(e) : "r"(t0), "r"(t1));
  asm("fma.rn.f16x2 %0, %1, %2, %3;" : "=r"(q) : "r"(y), "r"(c_alpha), "r"(0xA50DA50Du));
  asm("fma.rn.f16x2 %0, %1, %1, %2;" : "=r"(r) : "r"(q), "r"(0x14591459u));
  return r + (e >> 1);
}
constexpr int GATE = 4, POLY_MASK = 0xFF20;
struct ExpConst { uint32_t sel, alpha, zero; };
__device__ __forceinline__ void exp_chunk(float (&s)[32], uint32_t (&p)[16], const ExpConst& c) {
  uint32_t cs = c.sel;
#pragma unroll
  for (int i = 0; i < 16; i++) {
    if ((POLY_MASK >> i) & 1) {
      p[i] = exp2_pair_alu(s[2 * i], s[2 * i + 1], cs, c.alpha);
    } else {
      p[i] = pack_bf16(ex2(s[2 * i]), ex2(s[2 * i + 1]));
      if (i == GATE) asm("lop3.b32 %0, %1, %2, %3, 0xF8;" : "=r"(cs) : "r"(cs), "r"(p[i]), "r"(c.zero));
    }
  }
}
__device__ __forceinline__ void adv(uint64_t& d, uint32_t delta) {
  asm volatile("{\n.reg .b32 lo, hi;\nmov.b64 {lo, hi}, %0;\nadd.u32 lo, lo, %1;\nmov.b64 %0, {lo, hi};\n}\n" : "+l"(d) : "r"(delta));
}
__device__ __forceinline__ void qk_issue(float (&s)[32], uint64_t dq0, uint64_t dq1, uint64_t dk0, uint64_t dk1) {
  wgmma_ss_n64<0, 0>(s, dq0, dk0, 0);
  wgmma_ss_n64<0, 0>(s, dq1, dk1, 1);
  wg_commit();
}
template <int ACC = 1>
__device__ __forceinline__ void pv_issue(float (&o)[20], uint32_t (&p)[16], const uint64_t (&dv)[4]) {
  wgmma_rs_n40<0>(o, p[0], p[1], p[2], p[3], dv[0], ACC);
  wgmma_rs_n40<0>(o, p[4], p[5], p[6], p[7], dv[1], 1);
  wgmma_rs_n40<0>(o, p[8], p[9], p[10], p[11], dv[2], 1);
  wgmma_rs_n40<0>(o, p[12], p[13], p[14], p[15], dv[3], 1);
  wg_commit();
}
__device__ __forceinline__ void safe_chunk(float (&s)[32], float (&o)[20], float& m0, float& m1, uint64_t dq, uint64_t dk, uint64_t dv) {
  uint32_t p[16];
  wg_fence();
  qk_issue(s, dq, dq + 2, dk, dk + 2);
  wg_wait<0>();
  pin(s);
  float x0 = m0, x1 = m1;
#pragma unroll
  for (int i = 0; i < 8; i++) {
    x0 = fmaxf(x0, fmaxf(s[4 * i], s[4 * i + 1]));
    x1 = fmaxf(x1, fmaxf(s[4 * i + 2], s[4 * i + 3]));
  }
  x0 = fmaxf(x0, __shfl_xor_sync(~0u, x0, 1)); x1 = fmaxf(x1, __shfl_xor_sync(~0u, x1, 1));
  x0 = fmaxf(x0, __shfl_xor_sync(~0u, x0, 2)); x1 = fmaxf(x1, __shfl_xor_sync(~0u, x1, 2));
  const float a0 = ex2(m0 - x0), a1 = ex2(m1 - x1);
  m0 = x0; m1 = x1;
#pragma unroll
  for (int i = 0; i < 5; i++) { o[4 * i] *= a0; o[4 * i + 1] *= a0; o[4 * i + 2] *= a1; o[4 * i + 3] *= a1; }
#pragma unroll
  for (int i = 0; i < 8; i++) {
    p[2 * i] = pack_bf16(ex2(s[4 * i] - x0), ex2(s[4 * i + 1] - x0));
    p[2 * i + 1] = pack_bf16(ex2(s[4 * i + 2] - x1), ex2(s[4 * i + 3] - x1));
  }
  pin(p); pin(o);
  wg_fence();
  const uint64_t dvv[4] = {dv, dv + 2, dv + 4, dv + 6};
  pv_issue(o, p, dvv);
  wg_wait<0>();
  pin(o);
}
__device__ __forceinline__ float rcp(float x) { float y; asm("rcp.approx.f32 %0, %1;" : "=f"(y) : "f"(x)); return y; }
template <int B>
__device__ __forceinline__ void pack_o(uint32_t (&po)[16], float (&o)[20]) {
  const float i0 = rcp(o[16]), i1 = rcp(o[18]);
#pragma unroll
  for (int j = 0; j < 8; j++) po[B + j] = pack_bf16(o[2 * j] * ((j & 1) ? i1 : i0), o[2 * j + 1] * ((j & 1) ? i1 : i0));
}
__device__ __forceinline__ void store_o(float (&o)[20], uint32_t addr0, uint32_t addr1) {
  const float i0 = rcp(o[16]), i1 = rcp(o[18]);
  stsm_x4(addr0, pack_bf16(o[0] * i0, o[1] * i0), pack_bf16(o[2] * i1, o[3] * i1), pack_bf16(o[4] * i0, o[5] * i0),
          pack_bf16(o[6] * i1, o[7] * i1));
  stsm_x4(addr1, pack_bf16(o[8] * i0, o[9] * i0), pack_bf16(o[10] * i1, o[11] * i1), pack_bf16(o[12] * i0, o[13] * i0),
          pack_bf16(o[14] * i1, o[15] * i1));
}


template <bool FIRST, int NACC>
__device__ __forceinline__ void k_issue(float (&acc)[NACC], int s, uint32_t ph, int cw) {
  mbar_wait(B_GFULL + 8 * s, ph);
  const uint64_t da = make_desc(SB + s * G_STAGE_BYTES + cw * 8192, 16, 1024, 1);
  const uint64_t db = make_desc(SB + s * G_STAGE_BYTES + G_BM * G_BK * 2, 8192, 1024, 1);
  wg_fence();
  if constexpr (NACC == 128) {
    wgmma_ss_n256_tb<0, 0>(acc, da, db, FIRST ? 0 : 1);
    wgmma_ss_n256_tb<2, 128>(acc, da, db, 1);
    wgmma_ss_n256_tb<4, 256>(acc, da, db, 1);
    wgmma_ss_n256_tb<6, 384>(acc, da, db, 1);
  } else {
    wgmma_ss_n192_tb<0, 0>(acc, da, db, FIRST ? 0 : 1);
    wgmma_ss_n192_tb<2, 128>(acc, da, db, 1);
    wgmma_ss_n192_tb<4, 256>(acc, da, db, 1);
    wgmma_ss_n192_tb<6, 384>(acc, da, db, 1);
  }
  wg_commit();
}
__device__ __forceinline__ void k_retire(int s_prev, bool lane0) {
  wg_wait<1>();
  if (lane0) mbar_arrive(B_GEMPTY + 8 * s_prev);
}
template <int G0, bool HAND_OFF = true>
__device__ __forceinline__ void stage_half(const uint32_t (&pk)[64], const Tile& t, uint32_t a_n, uint32_t a_t, int cw, bool lane0) {
#pragma unroll
  for (int j = 0; j < 2; j++) {
    if (G0 + j == 9 && t.nbox == 3) break;
    if (t.kind == 2) {
#pragma unroll
      for (int g = 4 * j; g < 4 * j + 4; g++)
        stsm_x4_t(a_t + g * 2048, pk[4 * (G0 + g)], pk[4 * (G0 + g) + 1], pk[4 * (G0 + g) + 2], pk[4 * (G0 + g) + 3]);
    } else {
#pragma unroll
      for (int g = 4 * j; g < 4 * j + 4; g++)
        stsm_x4((a_n + j * 8192) ^ ((g & 3) * 32), pk[4 * (G0 + g)], pk[4 * (G0 + g) + 1], pk[4 * (G0 + g) + 2], pk[4 * (G0 + g) + 3]);
    }
  }
  if (!HAND_OFF) return;
  fence_async_smem();
  __syncwarp();
  if (lane0) mbar_arrive(B_SFULL + 2 * G0 + 8 * cw);
}
template <int J>
__device__ __forceinline__ void stage_box(const uint32_t (&pk)[64], const Tile& t, uint32_t a_n, uint32_t a_t, int cw, bool lane0) {
  if (t.kind == 2) {
#pragma unroll
    for (int g = 0; g < 4; g++)
      stsm_x4_t(a_t + g * 2048, pk[4 * (4 * J + g)], pk[4 * (4 * J + g) + 1], pk[4 * (4 * J + g) + 2], pk[4 * (4 * J + g) + 3]);
  } else {
#pragma unroll
    for (int g = 0; g < 4; g++)
      stsm_x4(a_n ^ (g * 32), pk[4 * (4 * J + g)], pk[4 * (4 * J + g) + 1], pk[4 * (4 * J + g) + 2], pk[4 * (4 * J + g) + 3]);
  }
  fence_async_smem();
  __syncwarp();
  if (lane0) mbar_arrive(B_SFULL + 16 * (J & 1) + 8 * cw);
}
__device__ __forceinline__ void row_norms(const uint32_t (&pk)[64], const Tile& t, int cw, int warp, int lane) {
  if (t.kind == 3) return;
  uint32_t n[8];
#pragma unroll
  for (int h = 0; h < 8; h++) {
    uint32_t n0 = 0, n1 = 0;
#pragma unroll
    for (int i = 0; i < 4; i++) {
      n0 = hfma2_bf16(pk[8 * h + 2 * i], pk[8 * h + 2 * i], n0);
      n1 = hfma2_bf16(pk[8 * h + 2 * i + 1], pk[8 * h + 2 * i + 1], n1);
    }
    n[h] = hadd2_bf16(__byte_perm(n0, n1, 0x5410), __byte_perm(n0, n1, 0x7632));
  }
#pragma unroll
  for (int h = 0; h < 4; h++)
    n[h] = hadd2_bf16((lane & 1) ? n[h + 4] : n[h], __shfl_xor_sync(~0u, (lane & 1) ? n[h] : n[h + 4], 1));
#pragma unroll
  for (int h = 0; h < 2; h++) {
    n[h] = hadd2_bf16((lane & 2) ? n[h + 2] : n[h], __shfl_xor_sync(~0u, (lane & 2) ? n[h] : n[h + 2], 2));
    n[h] = max(n[h] << 16, n[h] & 0xFFFF0000u);
  }
  uint32_t m = max((lane & 4) ? n[1] : n[0], __shfl_xor_sync(~0u, (lane & 4) ? n[0] : n[1], 4));
  m = max(m, __shfl_xor_sync(~0u, m, 8));
  m = max(m, __shfl_xor_sync(~0u, m, 16));
  const int h = (lane & 1) * 4 + (lane & 2) + ((lane >> 2) & 1);
  const int head = (t.col0 + (h >> 1) * t.cstep) / DH + (h & 1);
  if (lane < 8 && h < 2 * t.nbox) g_nrm[((t.br * 3 + t.kind) * NH + head) * (SEQ / 16) + t.mt * 8 + cw * 4 + warp] = m;
}
template <int NACC>
__device__ __forceinline__ void pack_tile(uint32_t (&pk)[64], float (&acc)[NACC], bool scale) {
  if (NACC == 128 && scale) {
#pragma unroll
    for (int j = 0; j < NACC / 2; j++) pk[j] = pack_bf16(acc[2 * j] * Q_SCALE, acc[2 * j + 1] * Q_SCALE);
  } else {
#pragma unroll
    for (int j = 0; j < NACC / 2; j++) pk[j] = pack_bf16(acc[2 * j], acc[2 * j + 1]);
  }
#pragma unroll
  for (int j = NACC / 2; j < 64; j++) pk[j] = 0;
}
__device__ __forceinline__ void load_b(const Params& P, const Tile& t, int kb, int s) {
  const CUtensorMap* m = t.kind == 3 ? &P.wo[t.br] : &P.wqkv[t.br];
  const int col = (t.kind == 3 ? 0 : t.kind * DM) + t.col0;
  mbar_expect_tx(B_GFULL + 8 * s, G_BM * G_BK * 2 + t.nbox * 8192);
#pragma unroll
  for (int j = 0; j < 4; j++)
    if (j < t.nbox) tma_load_2d(SB + s * G_STAGE_BYTES + G_BM * G_BK * 2 + j * 8192, m, col + j * t.cstep, kb * G_BK, B_GFULL + 8 * s);
}
__device__ __forceinline__ void load_a(const Params& P, const Tile& t, int kb, int s) {
  tma_load_2d(SB + s * G_STAGE_BYTES, t.kind == 3 ? &P.o_ld : &P.x[t.br], kb * G_BK, (t.kind == 3 ? t.br * SEQ : 0) + t.mt * G_BM,
              B_GFULL + 8 * s);
}
__device__ __forceinline__ void store_box(const Params& P, const Tile& t, int j, uint32_t buf, int cw) {
  const int row = t.mt * G_BM + cw * 64, col = t.col0 + j * t.cstep;
  if (t.kind == 2) tma_store_2d(&P.vt_st, buf, row, t.br * DM + col);
  else if (t.kind == 3) tma_store_2d(&P.out_st, buf, t.br * DM + col, row);
  else tma_store_2d(&P.qk_st, buf, t.kind * DM + col, t.br * SEQ + row);
}
__device__ __forceinline__ void store_half(const Params& P, const Tile& t, int pass, uint32_t buf, int cw) {
  store_box(P, t, 2 * pass, buf, cw);
  if (2 * pass + 1 < t.nbox) store_box(P, t, 2 * pass + 1, buf + 8192, cw);
  bulk_commit();
}
__device__ __forceinline__ void wait_o(const Tile& t, int quarter) {
  wait_count(&g_sync.o_done[(t.br * 8 + (t.mt >> 1)) * 4 + quarter], 16);
  fence_async_global();
}

__global__ void __launch_bounds__(384, 1) mha2_kernel(const __grid_constant__ Params P) {
  extern __shared__ uint8_t smem_raw[];
  if (smem_u32(smem_raw) != SB) __trap();
  const int wg = __shfl_sync(~0u, threadIdx.x >> 7, 0), warp = __shfl_sync(~0u, (threadIdx.x >> 5) & 3, 0);
  const int lane = threadIdx.x & 31;

  const int n1 = phase1_tiles(), n2 = is_helper() ? 0 : A_PER_CTA;

  if (wg == 0 && warp == 0) {
    const Tile t = phase1_tile(0);
    if (elect_one()) {
#pragma unroll
      for (int s = 0; s < G_STAGES; s++) mbar_init(B_GFULL + 8 * s, 1);
      fence_mbar_init();
      fence_async_smem();
      load_b(P, t, 0, 0);
      load_a(P, t, 0, 0);
    }
  }
  if (threadIdx.x == 32) {
    for (int s = 0; s < G_STAGES; s++) mbar_init(B_GEMPTY + 8 * s, 8);
    for (int s = 0; s < A_STAGES; s++) { mbar_init(B_KFULL + 8 * s, 1); mbar_init(B_KEMPTY + 8 * s, 8); }
    for (int s = 0; s < 2; s++) {
      mbar_init(B_SFULL + 8 * s, 4); mbar_init(B_SFULL + 16 + 8 * s, 4); mbar_init(B_SEMPTY + 8 * s, 1);
      mbar_init(B_QFULL + 8 * s, 2); mbar_init(B_QEMPTY + 8 * s, 8);
    }
    mbar_init(B_DUMMY, 8); mbar_init(B_ADONE, 8); mbar_init(B_AREADY, 1); mbar_init(B_STGFREE, 2);
    fence_mbar_init();
    sts(I_CONST, 0x6420u); sts(I_CONST + 4, 0x229F229Fu); sts(I_CONST + 8, 0);
  }
  __syncthreads();

  if (wg == 0) {
    reg_dec<40>();
    const bool one = elect_one();
    if (warp == 0) {
      for (int i = 0; i < n1; i++) {
        const Tile t = phase1_tile(i);
#pragma unroll 1
        for (int kb = i ? 0 : 1; kb < G_KB; kb++) {
          if (t.kind == 3 && (kb & 3) == 0) wait_o(t, kb >> 2);
          mbar_wait_sleep<32>(B_GEMPTY + 8 * (kb & 3), ((kb >> 2) & 1) ^ 1);
          if (one) { load_b(P, t, kb, kb & 3); load_a(P, t, kb, kb & 3); }
        }
      }
      int s = 0; uint32_t ph = 1;
      for (int i = 0; i < n2; i++) {
        const Unit u = attn_unit(i);
        wait_count(&g_sync.qkv_done[u.br * 4 + (u.head >> 3)], qkv_target(u.br));
        fence_async_global();
        if (i == 0) {
          mbar_wait_sleep<32>(B_GEMPTY, 1);
          mbar_wait_sleep<32>(B_GEMPTY + 8, 1);
          if (one) mbar_arrive(B_AREADY);
        }
#pragma unroll 1
        for (int kb = 0; kb < A_NKB; kb++) {
          mbar_wait_sleep(B_KEMPTY + 8 * s, ph);
          const uint32_t sk = OFF_KV + s * A_KV_BYTES;
          if (one) {
            mbar_expect_tx(B_KFULL + 8 * s, A_KV_TX);
            tma_load_2d(sk, &P.k_ld, DM + u.head * DH, u.br * SEQ + kb * 128, B_KFULL + 8 * s);
            tma_load_2d(sk + 8192, &P.vt_ld, kb * 128, u.br * DM + u.head * DH, B_KFULL + 8 * s);
            tma_load_2d(sk + 8192 + 5120, &P.vt_ld, kb * 128 + 64, u.br * DM + u.head * DH, B_KFULL + 8 * s);
          }
          if (++s == A_STAGES) { s = 0; ph ^= 1; }
        }
      }
      if (n2) {
        const Tile ot = out_tile();
        mbar_wait_sleep(B_STGFREE, 0);
#pragma unroll 1
        for (int kb = 0; kb < G_KB; kb++) {
          const int gs = (kb + 2) & 3;
          if (kb == 2) mbar_wait_sleep<32>(B_ADONE, 0);
          mbar_wait_sleep<32>(B_GEMPTY + 8 * gs, ((kb >> 2) & 1) ^ 1);
          if (one) load_b(P, ot, kb, gs);
          if (kb == 1) {
            wait_o(ot, 0);
            if (one) load_a(P, ot, 0, 2);
          }
          if (kb && (kb & 3) == 0) wait_o(ot, kb >> 2);
          if (kb >= 1 && one) load_a(P, ot, kb, gs);
        }
      }
      if (one) leave();
    } else if (warp <= 2) {
      const int cw = warp - 1;
      uint32_t ph;
      auto signal_tile = [&](const Tile& t) {
        if (t.kind == 3) return;
        bulk_wait<0>();
        if (t.cstep == 64) signal_add(&g_sync.qkv_done[t.br * 4 + t.col0 / G_BN]);
        else for (int j = 0; j < 4; j++) signal_add(&g_sync.qkv_done[t.br * 4 + j]);
      };
      for (int i = 0; i < n1 - 1; i++) {
        const Tile t = phase1_tile(i);
#pragma unroll 1
        for (int j = 0; j < 4; j++) {
          mbar_wait_sleep<32>(B_SFULL + 16 * (j & 1) + 8 * cw, j >> 1);
          if (one) {
            store_box(P, t, j, OFF_STG + cw * 16384, cw);
            bulk_commit();
            bulk_wait_read<0>();
            mbar_arrive(B_SEMPTY + 8 * cw);
            if (j == 3) signal_tile(t);
          }
        }
      }
      {
        const Tile t = phase1_tile(n1 - 1);
#pragma unroll
        for (int pass = 0; pass < 2; pass++) {
          mbar_wait_sleep<32>(B_SFULL + 16 * pass + 8 * cw, 0);
          if (one) store_half(P, t, pass, (pass ? SB + 2 * G_STAGE_BYTES : OFF_STG) + cw * 16384, cw);
        }
        if (one) {
          bulk_wait_read<0>();
          mbar_arrive(B_SEMPTY + 8 * cw);
          mbar_arrive(B_STGFREE);
          signal_tile(t);
        }
      }
      ph = 1;
      for (int i = 0; i < n2; i++) {
        const Unit u = attn_unit(i);
        mbar_wait_sleep<64>(B_SFULL + 8 * cw, ph);
        ph ^= 1;
        if (one) {
          tma_store_2d(&P.o_st, OFF_O + cw * 8192, u.head * DH, u.br * SEQ + u.qb * 256 + cw * 128);
          bulk_commit();
          bulk_wait<0>();
          signal_add(&g_sync.o_done[(u.br * 8 + u.qb) * 4 + (u.head >> 3)]);
          mbar_arrive(B_SEMPTY + 8 * cw);
        }
      }
      if (one) leave();
      if (n2) {
#pragma unroll
        for (int pass = 0; pass < 2; pass++) {
          mbar_wait_sleep<32>(B_SFULL + 16 * pass + 8 * cw, pass ? 1 : ph);
          const Tile t = out_tile();
          if (one) store_half(P, t, pass, SB + (2 + pass) * G_STAGE_BYTES + cw * 16384, cw);
        }
      }
      if (one) bulk_wait_read<0>();
    } else {
      for (int i = 0; i < n2; i++) {
        const Unit u = attn_unit(i);
        const uint32_t b = i & 1;
        wait_count(&g_sync.qkv_done[u.br * 4 + (u.head >> 3)], qkv_target(u.br));
        fence_async_global();
        const uint32_t* nq = g_nrm + ((u.br * 3 + 0) * NH + u.head) * (SEQ / 16);
        const uint4 k4 = __ldcg(reinterpret_cast<const uint4*>(nq + NH * (SEQ / 16)) + lane);
        const uint4 v4 = __ldcg(reinterpret_cast<const uint4*>(nq + 2 * NH * (SEQ / 16)) + lane);
        const uint32_t q1 = __ldcg(nq + u.qb * 16 + (lane & 15));
        const float kn = __uint_as_float(__reduce_max_sync(~0u, max(max(k4.x, k4.y), max(k4.z, k4.w))));
        const float vn = __uint_as_float(__reduce_max_sync(~0u, max(max(v4.x, v4.y), max(v4.z, v4.w))));
        const float qn0 = __uint_as_float(__reduce_max_sync(~0u, (lane & 8) ? 0u : q1));
        const float qn1 = __uint_as_float(__reduce_max_sync(~0u, (lane & 8) ? q1 : 0u));
        const bool v_ok = vn >= 1e-18f && vn <= 1e18f;
        mbar_wait_sleep<32>(i == 0 ? B_AREADY : i == 1 ? B_STGFREE : B_QEMPTY + 8 * b, 0);
        if (one) {
          mbar_expect_tx(B_QFULL + 8 * b, A_Q_BYTES);
          tma_load_2d(b ? OFF_Q1 : OFF_Q0, &P.q_ld, u.head * DH, u.br * SEQ + u.qb * 256, B_QFULL + 8 * b);
        }
        if (i == 0) {
          for (int j = lane; j < A_STAGES * 2 * 64; j += 32) {
            const uint32_t a = OFF_KV + (j >> 7) * A_KV_BYTES + 8192 + ((j >> 6) & 1) * 5120 + 4096 + (j & 63) * 16;
            asm volatile("st.shared.v4.b32 [%0], {%1, %1, %1, %1};" ::"r"(a), "r"(0x3F803F80u) : "memory");
          }
          fence_async_smem();
          __syncwarp();
        }
        if (one) {
          sts(I_FAST + 8 * b, (v_ok && qn0 * kn <= 4096.f) ? 1u : 0u);
          sts(I_FAST + 8 * b + 4, (v_ok && qn1 * kn <= 4096.f) ? 1u : 0u);
          mbar_arrive(B_QFULL + 8 * b);
        }
      }
      if (one) leave();
    }
  } else {
    reg_inc<232>();
    const int cw = wg - 1;
    const bool lane0 = elect_one();
    uint32_t sph = 1;
    const int srow = warp * 16 + (lane & 7) + ((lane >> 3) & 1) * 8;
    const uint32_t a_n = cw * 16384 + srow * 128 + (((lane >> 4) ^ (srow & 7)) << 4);
    const uint32_t a_t = cw * 16384 + ((lane >> 4) * 8 + (lane & 7)) * 128 + (((2 * warp + ((lane >> 3) & 1)) ^ (lane & 7)) << 4);
    auto stg_acquire = [&]() { mbar_wait(B_SEMPTY + 8 * cw, sph); sph ^= 1; };

    bool primed;
    uint32_t flag0;

    {
      uint32_t pk[64];
      Tile pt{0, 0, 0, 0, 0, 0};
      auto tile = [&](auto& acc, int i) {
        k_issue<true>(acc, 0, 0, cw);
        const int d0 = i == 0 ? -16 : is_helper() ? 1 : 1 + (int)(((blockIdx.x >> 1) & 7) * 6 >> 3), dd = is_helper() ? 2 : 3;
#pragma unroll 1
        for (int kb = 1; kb < G_KB; kb++) {
          k_issue<false>(acc, kb & 3, (kb >> 2) & 1, cw);
          if (kb == d0) { stg_acquire(); stage_box<0>(pk, pt, OFF_STG + a_n, OFF_STG + a_t, cw, lane0); }
          if (kb == d0 + 1) row_norms(pk, pt, cw, warp, lane);
          if (kb == d0 + dd) { stg_acquire(); stage_box<1>(pk, pt, OFF_STG + a_n, OFF_STG + a_t, cw, lane0); }
          if (kb == d0 + 2 * dd) { stg_acquire(); stage_box<2>(pk, pt, OFF_STG + a_n, OFF_STG + a_t, cw, lane0); }
          if (kb == d0 + 3 * dd) { stg_acquire(); stage_box<3>(pk, pt, OFF_STG + a_n, OFF_STG + a_t, cw, lane0); }
          k_retire((kb - 1) & 3, lane0);
        }
        wg_wait<0>();
        pin(acc);
        if (lane0) mbar_arrive(B_GEMPTY + 24);
        pt = phase1_tile(i);
        pack_tile(pk, acc, pt.kind == 0);
      };
      const int nwide = n1 - (phase1_tile(n1 - 1).nbox == 3);
#pragma unroll 1
      for (int i = 0; i < nwide; i++) { float acc[128]; tile(acc, i); }
      if (nwide < n1) { float acc[96]; tile(acc, nwide); }
      const bool free_ = mbar_test(B_SEMPTY + 8 * cw, sph) & mbar_test(B_GEMPTY + 16, 1);
      primed = mbar_test(B_QFULL, 0) & mbar_test(B_KFULL, 0);
      flag0 = lds_if(primed, I_FAST + 4 * cw);
      row_norms(pk, pt, cw, warp, lane);
      if (!free_) { mbar_wait(B_SEMPTY + 8 * cw, sph); mbar_wait(B_GEMPTY + 16, 1); }
      sph ^= 1;
      stage_half<0, false>(pk, pt, OFF_STG + a_n, OFF_STG + a_t, cw, lane0);
      stage_half<8>(pk, pt, SB + 2 * G_STAGE_BYTES + a_n, SB + 2 * G_STAGE_BYTES + a_t, cw, lane0);
      if (lane0) mbar_arrive(B_SFULL + 8 * cw);
    }

    const uint32_t o_addr = OFF_O + cw * 8192 + srow * 64 + (((lane >> 4) ^ ((srow >> 1) & 3)) << 4);
    uint32_t po[16] = {};
    bool o_pending = false;
    auto flush_o = [&]() {
      stsm_x4(o_addr, po[0], po[1], po[2], po[3]);
      stsm_x4(o_addr ^ 32, po[4], po[5], po[6], po[7]);
      stsm_x4(o_addr + 4096, po[8], po[9], po[10], po[11]);
      stsm_x4((o_addr + 4096) ^ 32, po[12], po[13], po[14], po[15]);
      fence_async_smem();
      __syncwarp();
      if (lane0) mbar_arrive(B_SFULL + 8 * cw);
    };
    {
      int s = 0; uint32_t ph = 0;
      const ExpConst ec{lds(I_CONST), lds(I_CONST + 4), lds(I_CONST + 8)};
      const uint32_t o_dump = OFF_DUMP + (lane & 7) * 64;
      int i = 0;
      while (i < n2) {
        if (!primed) {
          mbar_wait(B_QFULL + 8 * (i & 1), (i >> 1) & 1);
          flag0 = lds(I_FAST + 8 * (i & 1) + 4 * cw);
          mbar_wait(B_KFULL + 8 * s, ph);
        }
        primed = false;
        if (__all_sync(~0u, flag0 != 0)) {
          float sa[32], sb[32], oa[20], ob[20];
          uint32_t pa[16], pb[16], pa1[16], pb1[16];
          const uint64_t* dq = P.dq[(i & 1) * 2 + cw];
          uint64_t qa0 = dq[0], qa1 = dq[1], qb0 = dq[2], qb1 = dq[3];
          uint64_t ka0 = P.desc[s][0], ka1 = P.desc[s][1], kb0 = P.desc[s][12], kb1 = P.desc[s][13];
          uint64_t dv[4] = {P.desc[s][4], P.desc[s][5], P.desc[s][6], P.desc[s][7]};
          uint64_t dw[4] = {P.desc[s][8], P.desc[s][9], P.desc[s][10], P.desc[s][11]};
          wg_fence();
          qk_issue(sa, qa0, qa1, ka0, ka1);
          wg_wait<0>();
#pragma unroll
          for (int j = 0; j < 20; j++) { oa[j] = 1.f; ob[j] = 1.f; }
          bool next_fast;
          uint32_t o_a = o_dump, o_b = o_dump, bar_o = B_DUMMY;
          auto hand_off = [&]() {
            fence_async_smem();
            __syncwarp();
            if (lane0) mbar_arrive(bar_o);
          };
          do {
            const uint32_t bar_q = B_QEMPTY + 8 * (i & 1);
            const uint32_t qadv = (i & 1) ? 0u - ((OFF_Q1 - OFF_Q0) >> 4) : ((OFF_Q1 - OFF_Q0) >> 4);
            i++;
            const bool more = i < A_PER_CTA;
            uint32_t bar_prev;
            uint32_t padv = 0;
            auto stage = [&](auto first, auto last) {
              pin(sa); pin(oa); pin(ob); pin(pb1); wg_fence();
              qk_issue(sb, qb0, qb1, kb0, kb1);
              if (!first) pv_issue(ob, pb1, dw);
              if (first) store_o(oa, o_a, o_a ^ 32);
              exp_chunk(sa, pa, ec);
              wg_wait<first ? 0 : 1>();
              adv(kb0, 256); adv(kb1, 256); adv(ka0, 256); adv(ka1, 256);
              if (!first) { adv(dw[0], padv); adv(dw[1], padv); adv(dw[2], padv); adv(dw[3], padv); }
              pin(sb); pin(pa); pin(oa); wg_fence();
              qk_issue(sa, qa0, qa1, ka0, ka1);
              pv_issue<!first>(oa, pa, dv);
              if (first) store_o(ob, o_b, o_b ^ 32);
              exp_chunk(sb, pb, ec);
              wg_wait<1>();
              if (!first && lane0) mbar_arrive(bar_prev);
              bar_prev = B_KEMPTY + 8 * s;
              padv = A_KV_BYTES >> 4;
              if (++s == A_STAGES) { s = 0; ph ^= 1; padv = 0u - (A_STAGES - 1) * (A_KV_BYTES >> 4); }
              pin(sa); pin(pb); pin(ob); wg_fence();
              qk_issue(sb, qb0, qb1, kb0, kb1);
              pv_issue<!first>(ob, pb, dv);
              if (first) hand_off();
              bool ready = mbar_test(B_KFULL + 8 * s, ph);
              uint32_t flag = 0;
              if (last) {
                ready &= mbar_test(B_QFULL + 8 * (i & 1), (i >> 1) & 1) & mbar_test(B_SEMPTY + 8 * cw, sph);
                flag = lds_if(ready, I_FAST + 8 * (i & 1) + 4 * cw);
              }
              exp_chunk(sa, pa1, ec);
              wg_wait<1>();
              adv(dv[0], padv); adv(dv[1], padv); adv(dv[2], padv); adv(dv[3], padv);
              adv(kb0, padv - 256); adv(kb1, padv - 256); adv(ka0, padv - 256); adv(ka1, padv - 256);
              if (last) {
                if (!ready) {
                  mbar_wait(B_SEMPTY + 8 * cw, sph);
                  if (more) {
                    mbar_wait(B_QFULL + 8 * (i & 1), (i >> 1) & 1);
                    flag = lds(I_FAST + 8 * (i & 1) + 4 * cw);
                    if (flag) mbar_wait(B_KFULL + 8 * s, ph);
                  }
                }
                sph ^= 1;
                next_fast = __all_sync(~0u, more && flag != 0);
                if (next_fast) { adv(qa0, qadv); adv(qa1, qadv); adv(qb0, qadv); adv(qb1, qadv); }
                else { adv(ka0, 0u - padv); adv(ka1, 0u - padv); }
              } else if (!ready) {
                mbar_wait(B_KFULL + 8 * s, ph);
              }
              pin(sb); pin(pa1); wg_fence();
              qk_issue(sa, qa0, qa1, ka0, ka1);
              pv_issue(oa, pa1, dw);
              exp_chunk(sb, pb1, ec);
              if (last) {
                pin(pb1); wg_fence();
                pv_issue(ob, pb1, dw);
              }
              wg_wait<1>();
              if (last) { adv(dw[0], padv); adv(dw[1], padv); adv(dw[2], padv); adv(dw[3], padv); }
            };
            stage(BoolC<true>{}, BoolC<false>{});
#pragma unroll 1
            for (int kb = 1; kb < A_NKB - 1; kb++) stage(BoolC<false>{}, BoolC<false>{});
            stage(BoolC<false>{}, BoolC<true>{});
            wg_wait<0>();
            pin(oa); pin(ob); pin(sa);
            if (lane0) { mbar_arrive(bar_prev); mbar_arrive(bar_q); if (!more) mbar_arrive(B_ADONE); }
            o_a = o_addr; o_b = o_addr + 4096; bar_o = B_SFULL + 8 * cw;
          } while (next_fast);
          pack_o<0>(po, oa);
          pack_o<8>(po, ob);
          if (i < n2) flush_o();
          else o_pending = true;
        } else {
          float sa[32], oa[20], ob[20];
          float ma0 = -INFINITY, ma1 = -INFINITY, mb0 = -INFINITY, mb1 = -INFINITY;
          const uint64_t dq = P.dq[(i & 1) * 2 + cw][0];
#pragma unroll
          for (int j = 0; j < 20; j++) { oa[j] = 0.f; ob[j] = 0.f; }
#pragma unroll 1
          for (int kb = 0; kb < A_NKB; kb++) {
            mbar_wait(B_KFULL + 8 * s, ph);
#pragma unroll 1
            for (int c = 0; c < 2; c++) {
              safe_chunk(sa, oa, ma0, ma1, dq, P.desc[s][2 * c], P.desc[s][4 + 4 * c]);
              safe_chunk(sa, ob, mb0, mb1, dq + 256, P.desc[s][2 * c], P.desc[s][4 + 4 * c]);
            }
            if (lane0) mbar_arrive(B_KEMPTY + 8 * s);
            if (++s == A_STAGES) { s = 0; ph ^= 1; }
          }
          if (lane0) { mbar_arrive(B_QEMPTY + 8 * (i & 1)); if (i == A_PER_CTA - 1) mbar_arrive(B_ADONE); }
          i++;
          mbar_wait(B_STGFREE, 0);
          stg_acquire();
          store_o(oa, o_addr, o_addr ^ 32);
          store_o(ob, o_addr + 4096, (o_addr + 4096) ^ 32);
          fence_async_smem();
          __syncwarp();
          if (lane0) mbar_arrive(B_SFULL + 8 * cw);
        }
      }
    }

    if (n2) {
      const Tile t = out_tile();
      uint32_t pk[64];
      auto tile = [&](auto& acc) {
        k_issue<true>(acc, 2, 0, cw);
        if (o_pending) flush_o();
#pragma unroll 1
        for (int kb = 1; kb < G_KB; kb++) { k_issue<false>(acc, (kb + 2) & 3, (kb >> 2) & 1, cw); k_retire((kb + 1) & 3, lane0); }
        wg_wait<0>();
        pin(acc);
        pack_tile(pk, acc, false);
      };
      if (t.nbox == 4) { float acc[128]; tile(acc); }
      else { float acc[96]; tile(acc); }
      stg_acquire();
      mbar_wait(B_GEMPTY + 16, 1);
      stage_half<0>(pk, t, SB + 2 * G_STAGE_BYTES + a_n, 0, cw, lane0);
      mbar_wait(B_GEMPTY + 24, 1);
      stage_half<8>(pk, t, SB + 3 * G_STAGE_BYTES + a_n, 0, cw, lane0);
    }
  }
}

typedef CUresult (*EncodeFn)(CUtensorMap*, CUtensorMapDataType, cuuint32_t, void*, const cuuint64_t*, const cuuint64_t*,
                             const cuuint32_t*, const cuuint32_t*, CUtensorMapInterleave, CUtensorMapSwizzle,
                             CUtensorMapL2promotion, CUtensorMapFloatOOBfill);

void make_map(EncodeFn fn, CUtensorMap* m, const void* ptr, uint64_t cols, uint64_t rows, uint32_t box_c, uint32_t box_r,
              CUtensorMapSwizzle sw) {
  cuuint64_t dims[2] = {cols, rows};
  cuuint64_t strides[1] = {cols * 2};
  cuuint32_t box[2] = {box_c, box_r};
  cuuint32_t es[2] = {1, 1};
  fn(m, CU_TENSOR_MAP_DATA_TYPE_BFLOAT16, 2, const_cast<void*>(ptr), dims, strides, box, es, CU_TENSOR_MAP_INTERLEAVE_NONE,
     sw, CU_TENSOR_MAP_L2_PROMOTION_L2_128B, CU_TENSOR_MAP_FLOAT_OOB_FILL_NONE);
}

}

extern "C" void kernel_launch(void* const* d_in, const int* in_sizes, int n_in, void* d_out, int out_size) {
  (void)in_sizes; (void)n_in; (void)out_size;
  void* fnp = nullptr;
  cudaDriverEntryPointQueryResult qr;
  cudaGetDriverEntryPoint("cuTensorMapEncodeTiled", &fnp, cudaEnableDefault, &qr);
  EncodeFn fn = (EncodeFn)fnp;
  void *p_qk, *p_vt, *p_o;
  cudaGetSymbolAddress(&p_qk, g_qk);
  cudaGetSymbolAddress(&p_vt, g_vt);
  cudaGetSymbolAddress(&p_o, g_o);
  Params P;
  for (int b = 0; b < 2; b++) {
    make_map(fn, &P.x[b], d_in[3 * b + 0], DM, SEQ, 64, G_BM, CU_TENSOR_MAP_SWIZZLE_128B);
    make_map(fn, &P.wqkv[b], d_in[3 * b + 1], NQKV, DM, 64, G_BK, CU_TENSOR_MAP_SWIZZLE_128B);
    make_map(fn, &P.wo[b], d_in[3 * b + 2], DM, DM, 64, G_BK, CU_TENSOR_MAP_SWIZZLE_128B);
  }
  make_map(fn, &P.o_ld, p_o, DM, 2 * SEQ, 64, G_BM, CU_TENSOR_MAP_SWIZZLE_128B);
  make_map(fn, &P.qk_st, p_qk, 2 * DM, 2 * SEQ, 64, 64, CU_TENSOR_MAP_SWIZZLE_128B);
  make_map(fn, &P.vt_st, p_vt, SEQ, 2 * DM, 64, 64, CU_TENSOR_MAP_SWIZZLE_128B);
  make_map(fn, &P.out_st, d_out, 2 * DM, SEQ, 64, 64, CU_TENSOR_MAP_SWIZZLE_128B);
  make_map(fn, &P.q_ld, p_qk, 2 * DM, 2 * SEQ, DH, 256, CU_TENSOR_MAP_SWIZZLE_64B);
  make_map(fn, &P.k_ld, p_qk, 2 * DM, 2 * SEQ, DH, 128, CU_TENSOR_MAP_SWIZZLE_64B);
  make_map(fn, &P.vt_ld, p_vt, SEQ, 2 * DM, 64, DH, CU_TENSOR_MAP_SWIZZLE_128B);
  make_map(fn, &P.o_st, p_o, DM, 2 * SEQ, DH, 128, CU_TENSOR_MAP_SWIZZLE_64B);
  for (int i = 0; i < 16; i++)
    P.dq[i >> 2][i & 3] = make_desc(((i >> 3) ? OFF_Q1 : OFF_Q0) + ((i >> 2) & 1) * 8192 + ((i >> 1) & 1) * 4096 + (i & 1) * 32, 16, 512, 2);
  for (int st = 0; st < A_STAGES; st++) {
    const uint32_t kb = OFF_KV + st * A_KV_BYTES;
    for (int i = 0; i < 4; i++) P.desc[st][i] = make_desc(kb + (i >> 1) * 4096 + (i & 1) * 32, 16, 512, 2);
    for (int i = 0; i < 8; i++) P.desc[st][4 + i] = make_desc(kb + 8192 + (i >> 2) * 5120 + (i & 3) * 32, 16, 1024, 1);
    for (int i = 0; i < 2; i++) P.desc[st][12 + i] = P.desc[st][i];
    P.desc[st][14] = P.desc[st][15] = 0;
  }
  cudaFuncSetAttribute(mha2_kernel, cudaFuncAttributeMaxDynamicSharedMemorySize, SMEM_BYTES);
  int dev = 0, sms = 0;
  cudaGetDevice(&dev);
  cudaDeviceGetAttribute(&sms, cudaDevAttrMultiProcessorCount, dev);
  mha2_kernel<<<sms >= NCTA + NHELP ? NCTA + NHELP : NCTA, 384, SMEM_BYTES, cudaStreamPerThread>>>(P);
}
```
